```python
import torch

def _softmax(x, axis=-1):
    return torch.softmax(x, dim=axis)
def _gelu(x):
    return torch.nn.functional.gelu(x, approximate="tanh")
def _silu(x):
    return torch.nn.functional.silu(x)
def _sigmoid(x):
    return torch.sigmoid(x)
def _layernorm(x, axis=-1, eps=1e-5):
    m = x.mean(dim=axis, keepdim=True)
    v = x.var(dim=axis, keepdim=True, unbiased=False)
    return (x - m) / torch.sqrt(v + eps)
def _scatter_add(tgt, idx, src, axis=0):
    return tgt.clone().index_add_(axis, idx, src)
def _segment_sum(src, seg, n):
    out = torch.zeros((n,) + src.shape[1:], dtype=src.dtype)
    return out.index_add_(0, seg, src)
def _pad(x, pw):
    flat = tuple(v for pair in reversed(pw) for v in pair)
    return torch.nn.functional.pad(x, flat)

kernel_name = 'parallel_sum__sliding_block__glu_gated_glu__prompt'

def setup_inputs():

    _w = (lambda a: (lambda t: t.to(torch.bfloat16) if t.is_floating_point() else t)(torch.as_tensor(a)))
    def _A_setup():
        B, S, D = 1, 2048, 1024
        return {
            "x": _w((lambda *s: torch.randn(*s, dtype=torch.bfloat16) * 0.05)(B, S, D)),
            "wqkv": _w((lambda *s: torch.randn(*s, dtype=torch.bfloat16) * 0.05)(D, 3 * D)),
            "wo": _w((lambda *s: torch.randn(*s, dtype=torch.bfloat16) * 0.05)(D, D)),
        }
    _A_in = _A_setup()

    def _B_setup():
        B, S, D, F = 1, 2048, 1024, 3584
        return {
            "x": _w((lambda *s: torch.randn(*s, dtype=torch.bfloat16) * 0.05)(B, S, D)),
            "w_gate": _w((lambda *s: torch.randn(*s, dtype=torch.bfloat16) * 0.05)(D, F)),
            "w_up": _w((lambda *s: torch.randn(*s, dtype=torch.bfloat16) * 0.05)(D, F)),
            "w_down": _w((lambda *s: torch.randn(*s, dtype=torch.bfloat16) * 0.05)(F, D)),
        }
    _B_in = _B_setup()

    return {
        "A_x": _A_in["x"],
        "A_wqkv": _A_in["wqkv"],
        "A_wo": _A_in["wo"],
        "B_x": _B_in["x"],
        "B_w_gate": _B_in["w_gate"],
        "B_w_up": _B_in["w_up"],
        "B_w_down": _B_in["w_down"],
    }

def reference(A_x, A_wqkv, A_wo, B_x, B_w_gate, B_w_up, B_w_down):
    def _A_ref(x, wqkv, wo):
        B, S, D = x.shape
        H = 32; Dh = D // H; W = 256
        qkv = (lambda x, *d: x.permute(*d))((x @ wqkv).reshape(B, S, 3, H, Dh), 2, 0, 3, 1, 4)
        q, k, v = qkv[0], qkv[1], qkv[2]
        scores = torch.einsum("bhqd,bhkd->bhqk", q, k) * (Dh ** -0.5)
        idx = torch.arange(S)
        mask = (idx[:, None] - idx[None, :] >= 0) & (idx[:, None] - idx[None, :] < W)
        scores = torch.where(mask[None, None], scores, -1e9)
        p = _softmax(scores, axis=-1)
        o = torch.einsum("bhqk,bhkd->bhqd", p, v)
        return (lambda x, *d: x.permute(*d))(o, 0, 2, 1, 3).reshape(B, S, D) @ wo

    def _B_ref(x, w_gate, w_up, w_down):
        g = torch.einsum("bsd,df->bsf", x, w_gate)
        u = torch.einsum("bsd,df->bsf", x, w_up)
        h = _sigmoid(g) * u
        return torch.einsum("bsf,fd->bsd", h, w_down)

    x = A_x
    xn = _layernorm(x, axis=-1)
    return x + _A_ref(xn, A_wqkv, A_wo) + _B_ref(xn, B_w_gate, B_w_up, B_w_down)
```

```cpp
#include <cuda_runtime.h>
#include <cuda_bf16.h>
#include <cuda.h>
#include <stdint.h>

#define TRACE 0

namespace {

constexpr int STAGES = 4;
constexpr int STAGE_BYTES = 49152;
constexpr int OFF_RING = STAGES * STAGE_BYTES;
constexpr int OFF_BAR = OFF_RING + 32768;
constexpr int OFF_ST = OFF_BAR + 256;
constexpr int OFF_CS = OFF_ST + 1024;
constexpr int SMEM_BYTES = OFF_CS + 1024;
constexpr int B_FULL = 0, B_EMPTY = 32, B_AFULL = 64, B_XFULL = 128, B_XCH = 136, B_PDONE = 152, B_EPI = 160, B_OK = 200, B_ST = 232;
constexpr uint32_t SPIN_LIMIT = 1u << 22;

constexpr int C_XN = 0, C_KV = 16, C_HE = 144, C_HL = 160, C_O = 176, C_CS = 208, C_DONE = 216, C_NUM = 217;

__device__ __align__(1024) uint4 g_xn[2048 * 1024 / 8];
__device__ __align__(1024) uint4 g_qkv[3 * 2048 * 1024 / 8];
__device__ __align__(1024) uint4 g_h[2048 * 3584 / 8];
__device__ __align__(1024) uint4 g_o[2048 * 1024 / 8];
__device__ __align__(1024) float2 g_stat[2048];
__device__ __align__(1024) float2 g_cs[8 * 16 * 128];
__device__ __align__(1024) unsigned g_cnt[C_NUM * 8];
#define TRG(i, T) do {} while (0)
#define TRT(i, T) do {} while (0)
#define TR(i) do {} while (0)

__device__ __forceinline__ void wgmma_n256(float (&d)[128], uint64_t da, uint64_t db, int scaleD) {
  asm volatile("{\n.reg .pred p;\nsetp.ne.b32 p, %130, 0;\n"
    "wgmma.mma_async.sync.aligned.m64n256k16.f32.bf16.bf16 "
    "{%0, %1, %2, %3, %4, %5, %6, %7, %8, %9, %10, %11, %12, %13, %14, %15, %16, %17, %18, %19, %20, %21, %22, %23, %24, %25, %26, %27, %28, %29, %30, %31, %32, %33, %34, %35, %36, %37, %38, %39, %40, %41, %42, %43, %44, %45, %46, %47, %48, %49, %50, %51, %52, %53, %54, %55, %56, %57, %58, %59, %60, %61, %62, %63, %64, %65, %66, %67, %68, %69, %70, %71, %72, %73, %74, %75, %76, %77, %78, %79, %80, %81, %82, %83, %84, %85, %86, %87, %88, %89, %90, %91, %92, %93, %94, %95, %96, %97, %98, %99, %100, %101, %102, %103, %104, %105, %106, %107, %108, %109, %110, %111, %112, %113, %114, %115, %116, %117, %118, %119, %120, %121, %122, %123, %124, %125, %126, %127}, %128, %129, p, 1, 1, 0, 1;\n}\n"
    : "+f"(d[0]), "+f"(d[1]), "+f"(d[2]), "+f"(d[3]), "+f"(d[4]), "+f"(d[5]), "+f"(d[6]), "+f"(d[7]), "+f"(d[8]), "+f"(d[9]), "+f"(d[10]), "+f"(d[11]), "+f"(d[12]), "+f"(d[13]), "+f"(d[14]), "+f"(d[15]), "+f"(d[16]), "+f"(d[17]), "+f"(d[18]), "+f"(d[19]), "+f"(d[20]), "+f"(d[21]), "+f"(d[22]), "+f"(d[23]), "+f"(d[24]), "+f"(d[25]), "+f"(d[26]), "+f"(d[27]), "+f"(d[28]), "+f"(d[29]), "+f"(d[30]), "+f"(d[31]), "+f"(d[32]), "+f"(d[33]), "+f"(d[34]), "+f"(d[35]), "+f"(d[36]), "+f"(d[37]), "+f"(d[38]), "+f"(d[39]), "+f"(d[40]), "+f"(d[41]), "+f"(d[42]), "+f"(d[43]), "+f"(d[44]), "+f"(d[45]), "+f"(d[46]), "+f"(d[47]), "+f"(d[48]), "+f"(d[49]), "+f"(d[50]), "+f"(d[51]), "+f"(d[52]), "+f"(d[53]), "+f"(d[54]), "+f"(d[55]), "+f"(d[56]), "+f"(d[57]), "+f"(d[58]), "+f"(d[59]), "+f"(d[60]), "+f"(d[61]), "+f"(d[62]), "+f"(d[63]), "+f"(d[64]), "+f"(d[65]), "+f"(d[66]), "+f"(d[67]), "+f"(d[68]), "+f"(d[69]), "+f"(d[70]), "+f"(d[71]), "+f"(d[72]), "+f"(d[73]), "+f"(d[74]), "+f"(d[75]), "+f"(d[76]), "+f"(d[77]), "+f"(d[78]), "+f"(d[79]), "+f"(d[80]), "+f"(d[81]), "+f"(d[82]), "+f"(d[83]), "+f"(d[84]), "+f"(d[85]), "+f"(d[86]), "+f"(d[87]), "+f"(d[88]), "+f"(d[89]), "+f"(d[90]), "+f"(d[91]), "+f"(d[92]), "+f"(d[93]), "+f"(d[94]), "+f"(d[95]), "+f"(d[96]), "+f"(d[97]), "+f"(d[98]), "+f"(d[99]), "+f"(d[100]), "+f"(d[101]), "+f"(d[102]), "+f"(d[103]), "+f"(d[104]), "+f"(d[105]), "+f"(d[106]), "+f"(d[107]), "+f"(d[108]), "+f"(d[109]), "+f"(d[110]), "+f"(d[111]), "+f"(d[112]), "+f"(d[113]), "+f"(d[114]), "+f"(d[115]), "+f"(d[116]), "+f"(d[117]), "+f"(d[118]), "+f"(d[119]), "+f"(d[120]), "+f"(d[121]), "+f"(d[122]), "+f"(d[123]), "+f"(d[124]), "+f"(d[125]), "+f"(d[126]), "+f"(d[127])
    : "l"(da), "l"(db), "r"(scaleD));
}
__device__ __forceinline__ void wgmma_n128_lo(float (&d)[128], uint64_t da, uint64_t db, int scaleD) {
  asm volatile("{\n.reg .pred p;\nsetp.ne.b32 p, %66, 0;\n"
    "wgmma.mma_async.sync.aligned.m64n128k16.f32.bf16.bf16 "
    "{%0, %1, %2, %3, %4, %5, %6, %7, %8, %9, %10, %11, %12, %13, %14, %15, %16, %17, %18, %19, %20, %21, %22, %23, %24, %25, %26, %27, %28, %29, %30, %31, %32, %33, %34, %35, %36, %37, %38, %39, %40, %41, %42, %43, %44, %45, %46, %47, %48, %49, %50, %51, %52, %53, %54, %55, %56, %57, %58, %59, %60, %61, %62, %63}, %64, %65, p, 1, 1, 0, 1;\n}\n"
    : "+f"(d[0]), "+f"(d[1]), "+f"(d[2]), "+f"(d[3]), "+f"(d[4]), "+f"(d[5]), "+f"(d[6]), "+f"(d[7]), "+f"(d[8]), "+f"(d[9]), "+f"(d[10]), "+f"(d[11]), "+f"(d[12]), "+f"(d[13]), "+f"(d[14]), "+f"(d[15]), "+f"(d[16]), "+f"(d[17]), "+f"(d[18]), "+f"(d[19]), "+f"(d[20]), "+f"(d[21]), "+f"(d[22]), "+f"(d[23]), "+f"(d[24]), "+f"(d[25]), "+f"(d[26]), "+f"(d[27]), "+f"(d[28]), "+f"(d[29]), "+f"(d[30]), "+f"(d[31]), "+f"(d[32]), "+f"(d[33]), "+f"(d[34]), "+f"(d[35]), "+f"(d[36]), "+f"(d[37]), "+f"(d[38]), "+f"(d[39]), "+f"(d[40]), "+f"(d[41]), "+f"(d[42]), "+f"(d[43]), "+f"(d[44]), "+f"(d[45]), "+f"(d[46]), "+f"(d[47]), "+f"(d[48]), "+f"(d[49]), "+f"(d[50]), "+f"(d[51]), "+f"(d[52]), "+f"(d[53]), "+f"(d[54]), "+f"(d[55]), "+f"(d[56]), "+f"(d[57]), "+f"(d[58]), "+f"(d[59]), "+f"(d[60]), "+f"(d[61]), "+f"(d[62]), "+f"(d[63])
    : "l"(da), "l"(db), "r"(scaleD));
}
__device__ __forceinline__ void wgmma_n128_hi(float (&d)[128], uint64_t da, uint64_t db, int scaleD) {
  asm volatile("{\n.reg .pred p;\nsetp.ne.b32 p, %66, 0;\n"
    "wgmma.mma_async.sync.aligned.m64n128k16.f32.bf16.bf16 "
    "{%0, %1, %2, %3, %4, %5, %6, %7, %8, %9, %10, %11, %12, %13, %14, %15, %16, %17, %18, %19, %20, %21, %22, %23, %24, %25, %26, %27, %28, %29, %30, %31, %32, %33, %34, %35, %36, %37, %38, %39, %40, %41, %42, %43, %44, %45, %46, %47, %48, %49, %50, %51, %52, %53, %54, %55, %56, %57, %58, %59, %60, %61, %62, %63}, %64, %65, p, 1, 1, 0, 1;\n}\n"
    : "+f"(d[64]), "+f"(d[65]), "+f"(d[66]), "+f"(d[67]), "+f"(d[68]), "+f"(d[69]), "+f"(d[70]), "+f"(d[71]), "+f"(d[72]), "+f"(d[73]), "+f"(d[74]), "+f"(d[75]), "+f"(d[76]), "+f"(d[77]), "+f"(d[78]), "+f"(d[79]), "+f"(d[80]), "+f"(d[81]), "+f"(d[82]), "+f"(d[83]), "+f"(d[84]), "+f"(d[85]), "+f"(d[86]), "+f"(d[87]), "+f"(d[88]), "+f"(d[89]), "+f"(d[90]), "+f"(d[91]), "+f"(d[92]), "+f"(d[93]), "+f"(d[94]), "+f"(d[95]), "+f"(d[96]), "+f"(d[97]), "+f"(d[98]), "+f"(d[99]), "+f"(d[100]), "+f"(d[101]), "+f"(d[102]), "+f"(d[103]), "+f"(d[104]), "+f"(d[105]), "+f"(d[106]), "+f"(d[107]), "+f"(d[108]), "+f"(d[109]), "+f"(d[110]), "+f"(d[111]), "+f"(d[112]), "+f"(d[113]), "+f"(d[114]), "+f"(d[115]), "+f"(d[116]), "+f"(d[117]), "+f"(d[118]), "+f"(d[119]), "+f"(d[120]), "+f"(d[121]), "+f"(d[122]), "+f"(d[123]), "+f"(d[124]), "+f"(d[125]), "+f"(d[126]), "+f"(d[127])
    : "l"(da), "l"(db), "r"(scaleD));
}
__device__ __forceinline__ void wgmma_qk(float (&d)[32], uint32_t a0, uint32_t a1, uint32_t a2, uint32_t a3, uint64_t db, int scaleD) {
  asm volatile("{\n.reg .pred p;\nsetp.ne.b32 p, %37, 0;\n"
    "wgmma.mma_async.sync.aligned.m64n64k16.f32.bf16.bf16 "
    "{%0, %1, %2, %3, %4, %5, %6, %7, %8, %9, %10, %11, %12, %13, %14, %15, %16, %17, %18, %19, %20, %21, %22, %23, %24, %25, %26, %27, %28, %29, %30, %31}, {%32, %33, %34, %35}, %36, p, 1, 1, 0;\n}\n"
    : "+f"(d[0]), "+f"(d[1]), "+f"(d[2]), "+f"(d[3]), "+f"(d[4]), "+f"(d[5]), "+f"(d[6]), "+f"(d[7]), "+f"(d[8]), "+f"(d[9]), "+f"(d[10]), "+f"(d[11]), "+f"(d[12]), "+f"(d[13]), "+f"(d[14]), "+f"(d[15]), "+f"(d[16]), "+f"(d[17]), "+f"(d[18]), "+f"(d[19]), "+f"(d[20]), "+f"(d[21]), "+f"(d[22]), "+f"(d[23]), "+f"(d[24]), "+f"(d[25]), "+f"(d[26]), "+f"(d[27]), "+f"(d[28]), "+f"(d[29]), "+f"(d[30]), "+f"(d[31])
    : "r"(a0), "r"(a1), "r"(a2), "r"(a3), "l"(db), "r"(scaleD));
}
__device__ __forceinline__ void wgmma_pv(float (&d)[16], uint32_t a0, uint32_t a1, uint32_t a2, uint32_t a3, uint64_t db, int scaleD) {
  asm volatile("{\n.reg .pred p;\nsetp.ne.b32 p, %21, 0;\n"
    "wgmma.mma_async.sync.aligned.m64n32k16.f32.bf16.bf16 "
    "{%0, %1, %2, %3, %4, %5, %6, %7, %8, %9, %10, %11, %12, %13, %14, %15}, {%16, %17, %18, %19}, %20, p, 1, 1, 1;\n}\n"
    : "+f"(d[0]), "+f"(d[1]), "+f"(d[2]), "+f"(d[3]), "+f"(d[4]), "+f"(d[5]), "+f"(d[6]), "+f"(d[7]), "+f"(d[8]), "+f"(d[9]), "+f"(d[10]), "+f"(d[11]), "+f"(d[12]), "+f"(d[13]), "+f"(d[14]), "+f"(d[15])
    : "r"(a0), "r"(a1), "r"(a2), "r"(a3), "l"(db), "r"(scaleD));
}

__device__ __forceinline__ uint32_t smem_u32(const void* p) { return (uint32_t)__cvta_generic_to_shared(p); }
__device__ __forceinline__ void mbar_init(uint32_t bar, uint32_t cnt) { asm volatile("mbarrier.init.shared::cta.b64 [%0], %1;" ::"r"(bar), "r"(cnt) : "memory"); }
__device__ __forceinline__ void mbar_expect_tx(uint32_t bar, uint32_t bytes) { asm volatile("mbarrier.arrive.expect_tx.shared::cta.b64 _, [%0], %1;" ::"r"(bar), "r"(bytes) : "memory"); }
__device__ __forceinline__ void mbar_arrive(uint32_t bar) { asm volatile("mbarrier.arrive.shared::cta.b64 _, [%0];" ::"r"(bar) : "memory"); }
__device__ __forceinline__ uint32_t mapa(uint32_t addr, uint32_t cta) { uint32_t r; asm("mapa.shared::cluster.u32 %0, %1, %2;" : "=r"(r) : "r"(addr), "r"(cta)); return r; }
__device__ __forceinline__ void mbar_arrive_remote(uint32_t cluster_addr) { asm volatile("mbarrier.arrive.shared::cluster.b64 _, [%0];" ::"r"(cluster_addr) : "memory"); }
__device__ __forceinline__ bool mbar_try(uint32_t bar, uint32_t parity) {
  uint32_t ok;
  asm volatile("{\n.reg .pred p;\nmbarrier.try_wait.parity.shared::cta.b64 p, [%1], %2;\nselp.u32 %0, 1, 0, p;\n}" : "=r"(ok) : "r"(bar), "r"(parity) : "memory");
  return ok;
}
__device__ __forceinline__ bool mbar_test(uint32_t bar, uint32_t parity) {
  uint32_t ok;
  asm volatile("{\n.reg .pred p;\nmbarrier.test_wait.parity.shared::cta.b64 p, [%1], %2;\nselp.u32 %0, 1, 0, p;\n}" : "=r"(ok) : "r"(bar), "r"(parity) : "memory");
  return ok;
}
__device__ __forceinline__ void mbar_wait(uint32_t bar, uint32_t parity) {
  if (mbar_try(bar, parity)) return;
  uint32_t it = 0;
  while (!mbar_try(bar, parity)) { if (++it > SPIN_LIMIT) __trap(); }
}
__device__ __forceinline__ bool mbar_try_cluster(uint32_t bar, uint32_t parity) {
  uint32_t ok;
  asm volatile("{\n.reg .pred p;\nmbarrier.try_wait.parity.acquire.cluster.shared::cta.b64 p, [%1], %2;\nselp.u32 %0, 1, 0, p;\n}" : "=r"(ok) : "r"(bar), "r"(parity) : "memory");
  return ok;
}
__device__ __forceinline__ void mbar_wait_cluster(uint32_t bar, uint32_t parity) {
  uint32_t it = 0;
  while (!mbar_try_cluster(bar, parity)) { if (++it > SPIN_LIMIT) __trap(); }
}
__device__ __forceinline__ void bulk_g2s(uint32_t dst, const void* src, uint32_t bytes, uint32_t bar) {
  asm volatile("cp.async.bulk.shared::cluster.global.mbarrier::complete_tx::bytes [%0], [%1], %2, [%3];" ::"r"(dst), "l"(src), "r"(bytes), "r"(bar) : "memory");
}
__device__ __forceinline__ void tma2d(uint32_t dst, const CUtensorMap* m, int c0, int c1, uint32_t bar) {
  asm volatile("cp.async.bulk.tensor.2d.shared::cluster.global.mbarrier::complete_tx::bytes [%0], [%1, {%3, %4}], [%2];" ::"r"(dst), "l"(m), "r"(bar), "r"(c0), "r"(c1) : "memory");
}
__device__ __forceinline__ void tma5d_mc(uint32_t dst, const void* m, int c0, int c4, uint32_t bar, uint16_t mask) {
  asm volatile("cp.async.bulk.tensor.5d.shared::cluster.global.mbarrier::complete_tx::bytes.multicast::cluster [%0], [%1, {%3, %5, %5, %5, %4}], [%2], %6;"
               ::"r"(dst), "l"(m), "r"(bar), "r"(c0), "r"(c4), "r"(0), "h"(mask) : "memory");
}
__device__ __forceinline__ void tma5d(uint32_t dst, const CUtensorMap* m, int c0, int c4, uint32_t bar) {
  asm volatile("cp.async.bulk.tensor.5d.shared::cluster.global.mbarrier::complete_tx::bytes [%0], [%1, {%3, %5, %5, %5, %4}], [%2];" ::"r"(dst), "l"(m), "r"(bar), "r"(c0), "r"(c4), "r"(0) : "memory");
}
__device__ __forceinline__ void bulk_s2g(void* dst, uint32_t src, uint32_t bytes) {
  asm volatile("cp.async.bulk.global.shared::cta.bulk_group [%0], [%1], %2;" ::"l"(dst), "r"(src), "r"(bytes) : "memory");
}
__device__ __forceinline__ uint32_t tid_now() { uint32_t v; asm volatile("mov.u32 %0, %%tid.x;" : "=r"(v)); return v; }
__device__ __forceinline__ uint32_t uni(uint32_t v) { return __shfl_sync(0xffffffffu, v, 0); }
__device__ __forceinline__ bool elect_one() {
  uint32_t p;
  asm volatile("{\n.reg .pred P;\nelect.sync _|P, 0xffffffff;\nselp.u32 %0, 1, 0, P;\n}" : "=r"(p));
  return p;
}
__device__ __forceinline__ void tma2d_store(const CUtensorMap* m, uint32_t src, int c0, int c1) {
  asm volatile("cp.async.bulk.tensor.2d.global.shared::cta.bulk_group [%0, {%2, %3}], [%1];" ::"l"(m), "r"(src), "r"(c0), "r"(c1) : "memory");
}
__device__ __forceinline__ void wg_fence() { asm volatile("wgmma.fence.sync.aligned;" ::: "memory"); }
__device__ __forceinline__ void wg_commit() { asm volatile("wgmma.commit_group.sync.aligned;" ::: "memory"); }
template <int N> __device__ __forceinline__ void wg_wait() { asm volatile("wgmma.wait_group.sync.aligned %0;" ::"n"(N) : "memory"); }
template <int N> __device__ __forceinline__ void fence_regs(float (&d)[N]) {
#pragma unroll
  for (int i = 0; i < N; i++) asm volatile("" : "+f"(d[i])::"memory");
}
template <int N> __device__ __forceinline__ void fence_regs(uint32_t (&d)[N]) {
#pragma unroll
  for (int i = 0; i < N; i++) asm volatile("" : "+r"(d[i])::"memory");
}
template <int OFF> __device__ __forceinline__ void fence_half(float (&d)[128]) {
#pragma unroll
  for (int i = 0; i < 64; i++) asm volatile("" : "+f"(d[OFF + i])::"memory");
}
template <int N> __device__ __forceinline__ void reg_inc() { asm volatile("setmaxnreg.inc.sync.aligned.u32 %0;" ::"n"(N)); }
template <int N> __device__ __forceinline__ void reg_dec() { asm volatile("setmaxnreg.dec.sync.aligned.u32 %0;" ::"n"(N)); }
__device__ __forceinline__ void cluster_arrive_relaxed() { asm volatile("barrier.cluster.arrive.relaxed.aligned;" ::: "memory"); }
__device__ __forceinline__ void cluster_wait() { asm volatile("barrier.cluster.wait.aligned;" ::: "memory"); }
__device__ __forceinline__ void bar_arrive(int id, int n) { asm volatile("bar.arrive %0, %1;" ::"r"(id), "r"(n) : "memory"); }
__device__ __forceinline__ void bar_sync(int id, int n) { asm volatile("bar.sync %0, %1;" ::"r"(id), "r"(n) : "memory"); }
__device__ __forceinline__ uint32_t pack_bf16(float lo, float hi) { uint32_t r; asm("cvt.rn.bf16x2.f32 %0, %1, %2;" : "=r"(r) : "f"(hi), "f"(lo)); return r; }
__device__ __forceinline__ float bf_lo(uint32_t v) { return __uint_as_float(v << 16); }
__device__ __forceinline__ float bf_hi(uint32_t v) { return __uint_as_float(v & 0xffff0000u); }
__device__ __forceinline__ float round_bf16(float x) { return __bfloat162float(__float2bfloat16_rn(x)); }
__device__ __forceinline__ float ex2(float x) { float r; asm("ex2.approx.ftz.f32 %0, %1;" : "=f"(r) : "f"(x)); return r; }
__device__ __forceinline__ float tanh_fast(float x) { float r; asm("tanh.approx.f32 %0, %1;" : "=f"(r) : "f"(x)); return r; }
__device__ __forceinline__ void st_global16(void* p, uint32_t a, uint32_t b, uint32_t c, uint32_t d) {
  asm volatile("st.global.v4.b32 [%0], {%1, %2, %3, %4};" ::"l"(p), "r"(a), "r"(b), "r"(c), "r"(d) : "memory");
}
__device__ __forceinline__ void st_shared16(uint32_t p, uint32_t a, uint32_t b, uint32_t c, uint32_t d) {
  asm volatile("st.shared.v4.b32 [%0], {%1, %2, %3, %4};" ::"r"(p), "r"(a), "r"(b), "r"(c), "r"(d) : "memory");
}
__device__ __forceinline__ void flag_signal(int idx) {
  asm volatile("fence.acq_rel.gpu;" ::: "memory");
  asm volatile("red.relaxed.gpu.global.add.u32 [%0], 1;" ::"l"(g_cnt + idx * 8) : "memory");
}
__device__ __forceinline__ bool flag_test(int idx, unsigned target) {
  unsigned v;
  asm volatile("ld.acquire.gpu.global.u32 %0, [%1];" : "=r"(v) : "l"(g_cnt + idx * 8) : "memory");
  return __all_sync(0xffffffffu, v >= target);
}
__device__ __forceinline__ void flag_wait(int idx, unsigned target) {
  unsigned v, it = 0;
  while (true) {
    asm volatile("ld.acquire.gpu.global.u32 %0, [%1];" : "=r"(v) : "l"(g_cnt + idx * 8) : "memory");
    if (__all_sync(0xffffffffu, v >= target)) break;
    if (++it > SPIN_LIMIT) __trap();
  }
  asm volatile("fence.proxy.async.global;" ::: "memory");
}

constexpr uint64_t DESC_A_SW128 = (1ull << 16) | (64ull << 32) | (1ull << 62);
constexpr uint64_t DESC_A_NOSW = (8ull << 16) | (64ull << 32);
constexpr uint64_t DESC_B = (512ull << 16) | (64ull << 32) | (1ull << 62);
constexpr uint64_t DESC_K = (8ull << 16) | (32ull << 32);
constexpr uint64_t DESC_V = (32ull << 16) | (8ull << 32);

struct Maps { const CUtensorMap *qkv, *g, *u, *d, *o, *x; };

__device__ __forceinline__ void load_b0(int n, int b, uint32_t sb, uint32_t full, const CUtensorMap* m, int g) {
  tma5d(sb + b * 8192, m, 1024 + (b >> 1) * 1024 + g * 128 + (b & 1) * 64, 2 * n, full);
}
struct Loader {
  const char* ptr;
  int c0, c4, next;
  uint32_t peer, dst;
  bool act, rel;
};
__device__ __forceinline__ char* head_ptr(int which, int g, int mt, int w) {
  return (char*)g_qkv + (size_t)(which * 32 + 4 * g) * 131072 + (mt * 16 + w * 2) * 512;
}
__device__ __forceinline__ void loader_event(Loader& ld, int m, int w, uint32_t sbase, const Maps& mp, int g, int rank, int mt, int mt2) {
  const int b = (w & 3) ^ 2 ^ (2 * rank);
  if (m == 20) {
    if (w == 5) { ld.act = true; ld.ptr += 4 * 16384; }
    ld.next = 22;
    return;
  }
  if (m == 22 || m == 27) {
    if (tid_now() % 32 == 0) {
      if (m == 22) {
        char* p = head_ptr(1, g, mt, w);
#pragma unroll
        for (int hh = 0; hh < 4; hh++) bulk_s2g(p + hh * 131072, sbase + OFF_RING + (w * 4 + hh) * 1024, 1024);
        asm volatile("cp.async.bulk.commit_group;" ::: "memory");
      } else {
        asm volatile("cp.async.bulk.wait_group 0;" ::: "memory");
        asm volatile("fence.proxy.async.global;" ::: "memory");
        mbar_arrive(sbase + OFF_BAR + B_EPI);
      }
    }
    __syncwarp();
    ld.next = m == 22 ? 27 : 32;
    return;
  }
  if (m == 16 && w == 2 && elect_one()) mbar_arrive(sbase + OFF_BAR + B_OK + 24);
  ld.rel = w == 1 || w == 6;
  ld.act = m > 3 && m < 116 && (w == 5 || w == 2 || w == 3 || (w < 2 && m >= 80));
  ld.peer = uni(m < 80 ? mapa(sbase, rank ^ 1) - sbase : 0);
  ld.dst = uni(w == 5 ? sbase : sbase + 16384 + b * 8192);
  ld.next = m == 3 ? 4 : m == 16 ? 20 : (m < 80 ? (m & ~15) + 16 : (m == 80 ? 100 : m + 8));
  if (m < 80) {
    const int t = m >> 4;
    const bool qkv = t == 0 || (t == 1 && b < 2);
    ld.c0 = qkv ? (t == 0 ? 1024 + (b >> 1) * 1024 : 0) + g * 128 + (b & 1) * 64 : (t == 1 ? g : 16 * t - 24 + 2 * g + (b >> 1)) * 64;
    ld.c4 = 2 * (m & 15);
    ld.ptr = w == 5 ? (const char*)(g_xn + mt * 16 * 1024) : (const char*)(qkv ? mp.qkv : ((b & 1) ? mp.u : mp.g));
    if (w == 5) {
      if (m == 16) ld.act = false;
      if (t == 0) ld.ptr = (const char*)mp.x;
      ld.c0 = 64 * m;
      ld.c4 = t == 0 ? mt * 128 : -1;
    }
  } else {
    ld.c0 = (g >> 1) * 256 + (b ^ (2 * rank)) * 64;
    const int k0 = m == 80 ? 20 * rank : (m == 100 ? 40 + 8 * rank : 8 * rank);
    ld.c4 = w == 5 ? -1 : 2 * k0;
    if (w == 5 && m < 116) mbar_wait(sbase + OFF_BAR + B_OK + (m == 80 ? 0 : (m == 100 ? 8 : 16)), 0);
    ld.ptr = w == 5 ? (const char*)(m < 108 ? g_h + (mt2 * 56 + k0) * 1024 : g_o + (mt2 * 16 + k0) * 1024) : (const char*)(m < 108 ? mp.d : mp.o);
  }
}
__device__ __forceinline__ void refill(Loader& ld, uint32_t full, uint32_t par, uint32_t so, int w) {
  if (ld.act) {
    mbar_wait(full + (B_EMPTY - B_FULL), par);
    if (w != 5) {
      if (elect_one()) {
        if (ld.peer) tma5d_mc(ld.dst + so * 16, ld.ptr, ld.c0, ld.c4, full, 3);
        else tma5d(ld.dst + so * 16, (const CUtensorMap*)ld.ptr, ld.c0, ld.c4, full);
      }
      ld.c4 += 2;
    } else {
      if (elect_one()) {
        mbar_expect_tx(full, STAGE_BYTES);
        if (ld.c4 < 0) bulk_g2s(ld.dst + so * 16, ld.ptr, 16384, full);
        else tma2d(ld.dst + so * 16, (const CUtensorMap*)ld.ptr, ld.c0, ld.c4, full);
      }
      if (ld.c4 < 0) ld.ptr += 16384;
      ld.c0 += 64;
    }
    __syncwarp();
  }
}

__device__ __forceinline__ void wait_full(uint32_t sbase, int n) { mbar_wait(sbase + OFF_BAR + B_FULL + (n & (STAGES - 1)) * 8, (n >> 2) & 1); }
__device__ __forceinline__ void release(const Loader& ld, uint32_t full) {
  if (ld.rel && elect_one()) {
    mbar_arrive(full + (B_EMPTY - B_FULL));
    mbar_arrive_remote(full + (B_EMPTY - B_FULL) + ld.peer);
  }
}
__device__ __forceinline__ void gemm_steps(float (&acc)[128], Loader& ld, bool SW, int n0, int n1, uint32_t sbase, int c, int w,
                                           const Maps& mp, int g, int rank, int mt, int mt2) {
  const uint32_t a0 = uni((SW ? (uint32_t)DESC_A_SW128 : (uint32_t)DESC_A_NOSW) | (((sbase & 0x3ffff) + c * 8192) >> 4));
  const uint32_t b0 = ((uint32_t)DESC_B | (((sbase & 0x3ffff) + 16384) >> 4));
  const uint64_t ahi = (uint64_t)uni((SW ? DESC_A_SW128 : DESC_A_NOSW) >> 32) << 32, bhi = DESC_B & 0xffffffff00000000ull;
  const uint32_t ka = uni(SW ? 2 : 16), full0 = uni(sbase + OFF_BAR + B_FULL);
  n1 = (n1);
  int n = n0;
  uint32_t pfull = full0 + ((n0 - 1) & (STAGES - 1)) * 8, ppar = ((n0 - 1) >> 2) & 1, pso = ((n0 - 1) & (STAGES - 1)) * (STAGE_BYTES >> 4);
#pragma unroll 1
  do {
    const uint32_t s = n & (STAGES - 1), full = full0 + s * 8, par = (n >> 2) & 1, so = s * (STAGE_BYTES >> 4), da = a0 + so, db = b0 + so;
    wg_wait<0>();
    fence_regs(acc);
    release(ld, pfull);
    mbar_wait(full, par);
    wg_fence();
#pragma unroll
    for (int kk = 0; kk < 4; kk++) wgmma_n256(acc, ahi | (da + kk * ka), bhi | (db + kk * 128), n | kk);
    wg_commit();
    if (n + 3 == ld.next) loader_event(ld, n + 3, w, sbase, mp, g, rank, mt, mt2);
    refill(ld, pfull, ppar, pso, w);
    pfull = full; ppar = par; pso = so;
  } while (++n < n1);
}
template <int HI>
__device__ __forceinline__ void half_step(float (&acc)[128], uint32_t sbase, int stage, int c, bool sw, int accumulate) {
  const uint32_t sa = (sbase & 0x3ffff) + stage * STAGE_BYTES;
  const uint64_t da = (sw ? DESC_A_SW128 : DESC_A_NOSW) | (uint64_t)((sa + c * 8192) >> 4);
  const uint64_t db = DESC_B | (uint64_t)((sa + 16384 + HI * 16384) >> 4);
  const uint32_t ka = sw ? 2 : 16;
#pragma unroll
  for (int kk = 0; kk < 4; kk++) {
    if (HI) wgmma_n128_hi(acc, da + kk * ka, db + kk * 128, accumulate | kk);
    else wgmma_n128_lo(acc, da + kk * ka, db + kk * 128, accumulate | kk);
  }
}
template <int OFF>
__device__ __forceinline__ void ln_apply(float (&acc)[128], const uint8_t* smem, int row, int q) {
  const float2 s0 = *(const float2*)(smem + OFF_ST + row * 8), s1 = *(const float2*)(smem + OFF_ST + row * 8 + 64);
#pragma unroll
  for (int j = 0; j < 16; j++) {
    const float2 cs = *(const float2*)(smem + OFF_CS + OFF * 8 + j * 32 + q * 8);
    float* a = acc + OFF + 4 * j;
    a[0] = fmaf(-s0.x, cs.x, a[0]) * s0.y; a[1] = fmaf(-s0.x, cs.y, a[1]) * s0.y;
    a[2] = fmaf(-s1.x, cs.x, a[2]) * s1.y; a[3] = fmaf(-s1.x, cs.y, a[3]) * s1.y;
  }
}
template <int OFF>
__device__ __forceinline__ void head_store(const float (&acc)[128], char* p) {
#pragma unroll
  for (int hh = 0; hh < 4; hh++) {
    const float* a = acc + OFF + 16 * hh;
    st_global16(p + hh * 131072, pack_bf16(a[0], a[1]), pack_bf16(a[4], a[5]), pack_bf16(a[8], a[9]), pack_bf16(a[12], a[13]));
    st_global16(p + hh * 131072 + 512, pack_bf16(a[2], a[3]), pack_bf16(a[6], a[7]), pack_bf16(a[10], a[11]), pack_bf16(a[14], a[15]));
  }
}
template <int OFF>
__device__ __forceinline__ void glu_store(const float (&acc)[128], char* p) {
#pragma unroll
  for (int u = 0; u < 2; u++) {
    const float* a = acc + OFF + 16 * u;
    float h[16];
#pragma unroll
    for (int i = 0; i < 16; i++) h[i] = fmaf(tanh_fast(a[i]), a[32 + i], a[32 + i]);
    st_global16(p + u * 512, pack_bf16(h[0], h[1]), pack_bf16(h[4], h[5]), pack_bf16(h[8], h[9]), pack_bf16(h[12], h[13]));
    st_global16(p + u * 512 + 1024, pack_bf16(h[2], h[3]), pack_bf16(h[6], h[7]), pack_bf16(h[10], h[11]), pack_bf16(h[14], h[15]));
  }
}

constexpr float SM_C = 4.0f * 1.4426950408889634f * 0.17677669529663687f;

template <bool FIRST>
__device__ __forceinline__ void softmax_block(float (&S)[32], uint32_t (&P)[16], float& m0, float& m1, float& l0, float& l1, float& a0, float& a1, bool valid = true) {
  float x0 = fmaxf(S[0], S[1]), x1 = fmaxf(S[2], S[3]);
#pragma unroll
  for (int j = 1; j < 8; j++) { x0 = fmaxf(x0, fmaxf(S[4 * j], S[4 * j + 1])); x1 = fmaxf(x1, fmaxf(S[4 * j + 2], S[4 * j + 3])); }
  x0 = fmaxf(x0, __shfl_xor_sync(0xffffffffu, x0, 1)); x1 = fmaxf(x1, __shfl_xor_sync(0xffffffffu, x1, 1));
  x0 = fmaxf(x0, __shfl_xor_sync(0xffffffffu, x0, 2)); x1 = fmaxf(x1, __shfl_xor_sync(0xffffffffu, x1, 2));
  if (!FIRST) {
    x0 = valid ? fmaxf(x0, m0) : m0; x1 = valid ? fmaxf(x1, m1) : m1;
    a0 = ex2((m0 - x0) * SM_C); a1 = ex2((m1 - x1) * SM_C);
  }
  m0 = x0; m1 = x1;
  const float n0 = valid ? -x0 * SM_C : -INFINITY, n1 = valid ? -x1 * SM_C : -INFINITY;
  float s0 = 0.f, s1 = 0.f;
#pragma unroll
  for (int j = 0; j < 8; j++) {
    float p0 = ex2(fmaf(S[4 * j], SM_C, n0)), p1 = ex2(fmaf(S[4 * j + 1], SM_C, n0));
    float p2 = ex2(fmaf(S[4 * j + 2], SM_C, n1)), p3 = ex2(fmaf(S[4 * j + 3], SM_C, n1));
    s0 += p0 + p1; s1 += p2 + p3;
    P[2 * j] = pack_bf16(p0, p1); P[2 * j + 1] = pack_bf16(p2, p3);
  }
  if (FIRST) { l0 = s0; l1 = s1; } else { l0 = fmaf(l0, a0, s0); l1 = fmaf(l1, a1, s1); }
}
__device__ __forceinline__ void issue_qk(float (&S)[32], const uint32_t (&Q)[8], uint32_t kaddr) {
  wgmma_qk(S, Q[0], Q[1], Q[2], Q[3], (DESC_K & 0xffffffff00000000ull) | (kaddr + (uint32_t)DESC_K), 0);
  wgmma_qk(S, Q[4], Q[5], Q[6], Q[7], (DESC_K & 0xffffffff00000000ull) | (kaddr + (uint32_t)DESC_K + 16), 1);
}
__device__ __forceinline__ void issue_pv(float (&O)[16], const uint32_t (&P)[16], uint32_t vaddr, int acc) {
#pragma unroll
  for (int t = 0; t < 4; t++) wgmma_pv(O, P[4 * t], P[4 * t + 1], P[4 * t + 2], P[4 * t + 3], (DESC_V & 0xffffffff00000000ull) | (vaddr + (uint32_t)DESC_V + t * 64), acc | t);
}
__device__ __forceinline__ void scale_o(float (&O)[16], float a0, float a1) {
#pragma unroll
  for (int j = 0; j < 4; j++) { O[4 * j] *= a0; O[4 * j + 1] *= a0; O[4 * j + 2] *= a1; O[4 * j + 3] *= a1; }
}
__device__ __forceinline__ void order_after(float l0, float l1) { if (__any_sync(0xffffffffu, fminf(l0, l1) < 0.0f)) __trap(); }
__device__ __forceinline__ void fill_ninf(float (&S)[32]) {
#pragma unroll
  for (int i = 0; i < 32; i++) asm volatile("mov.b32 %0, 0xff800000;" : "=f"(S[i]));
}
__device__ __forceinline__ void load_q(uint32_t (&Q)[8], int head, int qb, int warp, int lane) {
  const char* p = (const char*)g_qkv + (size_t)head * 131072 + (qb * 8 + warp * 2) * 512 + lane * 4;
#pragma unroll
  for (int i = 0; i < 8; i++)
    asm volatile("ld.global.L1::no_allocate.u32 %0, [%1];" : "=r"(Q[i]) : "l"(p + (i & 1) * 512 + (i >> 1) * 128) : "memory");
}

__global__ void __launch_bounds__(384, 1) __cluster_dims__(2, 1, 1)
fused_kernel(const __grid_constant__ CUtensorMap tmQKV, const __grid_constant__ CUtensorMap tmG, const __grid_constant__ CUtensorMap tmU,
             const __grid_constant__ CUtensorMap tmD, const __grid_constant__ CUtensorMap tmO, const __grid_constant__ CUtensorMap tmX,
             const __grid_constant__ CUtensorMap tmOut, const uint4* __restrict__ x, const uint4* __restrict__ wqkv) {
  extern __shared__ __align__(1024) uint8_t smem_raw[];
  const uint32_t sbase = __shfl_sync(0xffffffffu, smem_u32(smem_raw), 0);
  const uint32_t bars = sbase + OFF_BAR;
  const int tid = threadIdx.x, wid = __shfl_sync(0xffffffffu, tid >> 5, 0), wg = wid >> 2, warp = wid & 3, lane = tid & 31;
  const int rank = blockIdx.x & 1, cl = blockIdx.x >> 1, mp = cl & 7, g = cl >> 3;
  const int mt = 2 * mp + rank;
  const int mt2 = 2 * mp + (g & 1), nt2 = g >> 1;
  const Maps maps{&tmQKV, &tmG, &tmU, &tmD, &tmO, &tmX};
  TRT(63, 0);
  TRG(61, 0);

  if (wid == 0) {
    if (elect_one()) {
      asm volatile("prefetch.tensormap [%0];" ::"l"(&tmX) : "memory");
      asm volatile("prefetch.tensormap [%0];" ::"l"(&tmQKV) : "memory");
      for (int s = 0; s < STAGES; s++) { mbar_init(bars + B_FULL + s * 8, 1); mbar_init(bars + B_EMPTY + s * 8, 4); }
      for (int s = 0; s < 8; s++) mbar_init(bars + B_AFULL + s * 8, 1);
      for (int s = 0; s < 4; s++) mbar_init(bars + B_EPI + s * 8, 8);
      for (int s = 0; s < 4; s++) mbar_init(bars + B_OK + s * 8, 1);
      mbar_init(bars + B_ST, 128);
      mbar_init(bars + B_XFULL, 1); mbar_init(bars + B_XCH, 1); mbar_init(bars + B_XCH + 8, 1); mbar_init(bars + B_PDONE, 2);
      asm volatile("fence.mbarrier_init.release.cluster;" ::: "memory");
      asm volatile("fence.proxy.async.shared::cta;" ::: "memory");
      for (int s = 0; s < STAGES; s++) mbar_expect_tx(bars + B_FULL + s * 8, STAGE_BYTES);
      mbar_expect_tx(bars + B_XCH, 16384); mbar_expect_tx(bars + B_XCH + 8, 16384);
    }
    __syncwarp();
  }
  if (wg == 0) {
    bar_sync(1, 384);
    cluster_arrive_relaxed();
    {
      mbar_wait(bars + B_FULL, 0);
      const int row0 = g * 16 + warp * 4;
      const uint4* xp = x + (size_t)(mt * 128 + row0) * 128;
      asm volatile("prefetch.global.L2 [%0];" ::"l"(xp + lane * 16));
      asm volatile("prefetch.global.L2 [%0];" ::"l"(xp + lane * 16 + 8));
      uint4 v[4][4];
      const uint4* wp = wqkv + (size_t)(mt * 64 + warp * 16) * 384 + 128 + (lane >> 4) * 128 + g * 16 + (lane & 15);
#pragma unroll
      for (int i = 0; i < 16; i++) v[i >> 2][i & 3] = __ldg(wp + i * 384);
      float cs[8] = {0.f, 0.f, 0.f, 0.f, 0.f, 0.f, 0.f, 0.f};
#pragma unroll
      for (int i = 0; i < 16; i++) {
        const uint4 u = v[i >> 2][i & 3];
        cs[0] += bf_lo(u.x); cs[1] += bf_hi(u.x); cs[2] += bf_lo(u.y); cs[3] += bf_hi(u.y);
        cs[4] += bf_lo(u.z); cs[5] += bf_hi(u.z); cs[6] += bf_lo(u.w); cs[7] += bf_hi(u.w);
        v[i >> 2][i & 3] = __ldg(xp + (i >> 2) * 128 + (i & 3) * 32 + lane);
      }
      float* part = (float*)(smem_raw + OFF_RING);
      *(float4*)(part + warp * 256 + lane * 8) = make_float4(cs[0], cs[1], cs[2], cs[3]);
      *(float4*)(part + warp * 256 + lane * 8 + 4) = make_float4(cs[4], cs[5], cs[6], cs[7]);
      bar_sync(2, 128);
      float2 t = make_float2(0.f, 0.f);
#pragma unroll
      for (int i = 0; i < 4; i++) { const float2 u = *(const float2*)(part + i * 256 + tid * 2); t.x += u.x; t.y += u.y; }
      g_cs[(g * 16 + mt) * 128 + tid] = t;
#pragma unroll
      for (int rr = 0; rr < 4; rr++) {
        float f[32];
#pragma unroll
        for (int i = 0; i < 4; i++) {
          f[8 * i] = bf_lo(v[rr][i].x); f[8 * i + 1] = bf_hi(v[rr][i].x); f[8 * i + 2] = bf_lo(v[rr][i].y); f[8 * i + 3] = bf_hi(v[rr][i].y);
          f[8 * i + 4] = bf_lo(v[rr][i].z); f[8 * i + 5] = bf_hi(v[rr][i].z); f[8 * i + 6] = bf_lo(v[rr][i].w); f[8 * i + 7] = bf_hi(v[rr][i].w);
        }
        float s = 0.f;
#pragma unroll
        for (int i = 0; i < 32; i++) s += f[i];
#pragma unroll
        for (int o = 16; o > 0; o >>= 1) s += __shfl_xor_sync(0xffffffffu, s, o);
        const float mean = s * (1.0f / 1024.0f);
        float ss = 0.f;
#pragma unroll
        for (int i = 0; i < 32; i++) { const float d = f[i] - mean; ss = fmaf(d, d, ss); }
#pragma unroll
        for (int o = 16; o > 0; o >>= 1) ss += __shfl_xor_sync(0xffffffffu, ss, o);
        const uint32_t mb2 = pack_bf16(mean, mean);
        const float mb = bf_hi(mb2);
        const float sd = round_bf16(sqrtf(round_bf16(round_bf16(ss * (1.0f / 1024.0f)) + 1e-5f)));
        const float inv = 0.5f / sd;
        const int row = row0 + rr;
        if (lane == 0) g_stat[mt * 128 + row] = make_float2(mb, inv);
#pragma unroll
        for (int i = 0; i < 4; i++) {
          uint32_t w[4] = {v[rr][i].x, v[rr][i].y, v[rr][i].z, v[rr][i].w};
#pragma unroll
          for (int e = 0; e < 4; e++) {
            asm("sub.rn.bf16x2 %0, %0, %1;" : "+r"(w[e]) : "r"(mb2));
            w[e] = pack_bf16(bf_lo(w[e]) * inv, bf_hi(w[e]) * inv);
          }
          st_global16(g_xn + (mt * 16 + i * 4 + (lane >> 3)) * 1024 + row * 8 + ((lane & 7) ^ (row & 7)), w[0], w[1], w[2], w[3]);
        }
      }
      bar_sync(2, 128);
      if (tid == 0) TR(0);
      if (warp == 0) {
        if (elect_one()) {
          flag_signal(C_XN + mt);
          asm volatile("red.relaxed.gpu.global.add.u32 [%0], 1;" ::"l"(g_cnt + (C_CS + g) * 8) : "memory");
        }
        __syncwarp();
        flag_wait(lane ? C_XN + mt : C_CS + g, lane ? 8 : 16);
        __syncwarp();
        if (lane == 0) TR(1);
      }
      bar_sync(2, 128);
      auto load_xn = [&](int s) {
        if (warp == 1) {
          if (s == 0) mbar_wait(bars + B_OK + 24, 0);
          mbar_wait(bars + B_EMPTY + s * 8, 1);
          if (elect_one()) {
            asm volatile("fence.proxy.async.global;" ::: "memory");
            mbar_expect_tx(bars + B_FULL + s * 8, STAGE_BYTES);
            bulk_g2s(sbase + s * STAGE_BYTES, g_xn + (mt * 16 + s) * 1024, 16384, bars + B_FULL + s * 8);
          }
          __syncwarp();
        }
      };
      t = make_float2(0.f, 0.f);
#pragma unroll
      for (int i = 0; i < 16; i++) { const float2 u = __ldcg(g_cs + (g * 16 + i) * 128 + tid); t.x += u.x; t.y += u.y; }
      const float2 st2 = __ldcg(g_stat + mt * 128 + tid);
      load_xn(0);
      *(float2*)(smem_raw + OFF_CS + tid * 8) = t;
      *(float2*)(smem_raw + OFF_ST + tid * 8) = st2;
      mbar_arrive(bars + B_ST);
      if (tid == 0) TR(2);
      load_xn(1); load_xn(2); load_xn(3);
    }
    int st = 0;
    auto service = [&](bool block, int st_end) {
      while (st < st_end) {
        if (st == 0 || st == 2) {
          if (block) mbar_wait(bars + B_EPI + 16 + st * 4, 0);
          else if (!mbar_test(bars + B_EPI + 16 + st * 4, 0)) break;
          if (elect_one()) flag_signal((st == 0 ? C_HE : C_HL) + mt);
        } else {
          const int idx = st == 1 ? C_HE + mt2 : (st == 3 ? C_HL + mt2 : C_O + mt2 * 2 + rank);
          const unsigned target = st == 4 ? 4 : 8;
          if (block) flag_wait(idx, target);
          else { if (!flag_test(idx, target)) break; asm volatile("fence.proxy.async.global;" ::: "memory"); }
          if (elect_one()) mbar_arrive(bars + B_OK + (st >> 1) * 8);
        }
        __syncwarp();
        st++;
        if (!block) break;
      }
    };
    if (warp == 0) {
      mbar_wait(bars + B_EPI, 0);
      if (elect_one()) flag_signal(C_KV + mt * 8 + g);
      __syncwarp();
      if (lane == 0) TR(4);
      flag_wait(C_KV + max(mt - min(lane, 2), 0) * 8 + g, 1);
      __syncwarp();
      if (lane == 0) TR(5);
    }
    cluster_wait();
    auto kv_load = [&](int item, int e) {
      if (warp == 0 && item < 8) {
        const int kb = max(2 * mt + (item & 1) - 4 + (int)((0x3231240140ull >> (4 * e)) & 7), 0);
        const char* src = (const char*)g_qkv + (size_t)((32 + ((0x358 >> e) & 1) * 32 + 4 * g + (item >> 1)) * 32 + kb) * 4096;
        const uint32_t slot = (2 * item + e) & 7;
        const uint32_t bar = bars + B_AFULL + (uint32_t)((0x4322111044ull >> (4 * e)) & 7) * 8;
        if (elect_one()) {
          if (e == 2 || e == 8) mbar_expect_tx(bar, 4096);
          if (e == 3) mbar_expect_tx(bar, 12288);
          if (e == 6 || (e == 0 && item == 0)) mbar_expect_tx(bar, 8192);
          if (e == 9) mbar_expect_tx(bar, item < 7 ? 12288 : 4096);
          bulk_g2s(sbase + OFF_RING + slot * 4096, src, 4096, bar);
        }
      }
    };
#pragma unroll
    for (int e = 0; e < 8; e++) kv_load(0, e);
    mbar_wait(bars + B_EPI + 8, 0);
    if (tid == 0) TR(3);
    const int q = lane & 3, r = lane >> 2;
    int dlt = 16 * warp + r - 2 * q;
    const uint32_t ring = ((sbase & 0x3ffff) + OFF_RING) >> 4;
    auto grp_test = [&](int item, int gi) { return mbar_test(bars + B_AFULL + gi * 8, (item + (gi == 4)) & 1); };
    auto grp_wait = [&](int item, int gi, bool ok) { if (!ok) mbar_wait(bars + B_AFULL + gi * 8, (item + (gi == 4)) & 1); };
    auto slot = [&](int item, int e) { return ring + ((2 * item + e) & 7) * 256; };
    auto slot_free = [&](int item, int e) { if (e < 2) kv_load(item, e + 8); else kv_load(item + 1, e - 2); };
    float S0[32], S1[32], O[16];
    uint32_t Q[8], Pa[16], Pb[16];
    float m0, m1, l0, l1, a0, a1;
    load_q(Q, 4 * g, 2 * mt, warp, lane);
    grp_wait(-1, 4, false); grp_wait(0, 0, false);
    wg_fence();
    issue_qk(S0, Q, slot(0, 0)); issue_qk(S1, Q, slot(0, 1));
    wg_commit();
    wg_wait<0>();
    fence_regs(S0); fence_regs(S1);
#pragma unroll 1
    for (int it = 0; it < 8; it++) {
      const int item = uni(it);
      const int head = 4 * g + (item >> 1), qb = 2 * mt + (item & 1);
      asm volatile("" : "+r"(dlt));
      if (qb < 4) fill_ninf(S0);
#pragma unroll
      for (int j = 0; j < 8; j++) {
        S0[4 * j] = (8 * j <= dlt) ? S1[4 * j] : S0[4 * j];
        S0[4 * j + 1] = (8 * j + 1 <= dlt) ? S1[4 * j + 1] : S0[4 * j + 1];
        S0[4 * j + 2] = (8 * j - 8 <= dlt) ? S1[4 * j + 2] : S0[4 * j + 2];
        S0[4 * j + 3] = (8 * j - 7 <= dlt) ? S1[4 * j + 3] : S0[4 * j + 3];
      }
      fence_regs(S0);
      wg_fence();
      issue_qk(S1, Q, slot(item, 2));
      wg_commit();
      if (item > 0) slot_free(item - 1, 9);
      slot_free(item, 0); slot_free(item, 1);
      bool ok = grp_test(item, 1);
      softmax_block<true>(S0, Pa, m0, m1, l0, l1, a0, a1);
#pragma unroll
      for (int j = 0; j < 8; j++) {
#pragma unroll
        for (int hh = 0; hh < 2; hh++) {
          uint32_t old;
          asm("shl.b32 %0, -1, %1;" : "=r"(old) : "r"(max(16 * (dlt + 1) - 16 * (8 * j - 8 * hh), 0)));
          Pb[2 * j + hh] = Pa[2 * j + hh] & ~old;
          Pa[2 * j + hh] &= old;
        }
      }
      fence_regs(Pa); fence_regs(Pb);
      order_after(l0, l1);
      grp_wait(item, 1, ok);
      wg_wait<0>();
      fence_regs(S1);
      wg_fence();
      issue_pv(O, Pa, slot(item, 3), 0); issue_pv(O, Pb, slot(item, 4), 1); issue_qk(S0, Q, slot(item, 5));
      wg_commit();
      slot_free(item, 2);
      ok = grp_test(item, 2);
      uint32_t Pc[16];
      softmax_block<false>(S1, Pc, m0, m1, l0, l1, a0, a1, qb >= 3);
      fence_regs(Pc);
      order_after(l0, l1);
      grp_wait(item, 2, ok);
      wg_wait<0>();
      fence_regs(O); fence_regs(S0);
      scale_o(O, a0, a1);
      fence_regs(O);
      wg_fence();
      issue_pv(O, Pc, slot(item, 6), 1); issue_qk(S1, Q, slot(item, 7));
      wg_commit();
      slot_free(item, 3); slot_free(item, 4); slot_free(item, 5);
      if (warp == 0) service(false, 4);
      ok = grp_test(item, 3);
      softmax_block<false>(S0, Pa, m0, m1, l0, l1, a0, a1, qb >= 2);
      fence_regs(Pa);
      order_after(l0, l1);
      grp_wait(item, 3, ok);
      wg_wait<0>();
      fence_regs(O); fence_regs(S1);
      scale_o(O, a0, a1);
      fence_regs(O);
      wg_fence();
      issue_pv(O, Pa, slot(item, 8), 1);
      wg_commit();
      load_q(Q, 4 * g + (min(item + 1, 7) >> 1), 2 * mt + ((item + 1) & 1), warp, lane);
      slot_free(item, 6); slot_free(item, 7);
      ok = grp_test(item, 4);
      softmax_block<false>(S1, Pb, m0, m1, l0, l1, a0, a1, qb >= 1);
      fence_regs(Pb);
      order_after(l0, l1);
      grp_wait(item, 4, ok);
      wg_wait<0>();
      fence_regs(O);
      scale_o(O, a0, a1);
      fence_regs(O); fence_regs(Q);
      wg_fence();
      issue_pv(O, Pb, slot(item, 9), 1); issue_qk(S0, Q, slot(item, 10)); issue_qk(S1, Q, slot(item, 11));
      wg_commit();
      slot_free(item, 8);
      l0 += __shfl_xor_sync(0xffffffffu, l0, 1); l1 += __shfl_xor_sync(0xffffffffu, l1, 1);
      l0 += __shfl_xor_sync(0xffffffffu, l0, 2); l1 += __shfl_xor_sync(0xffffffffu, l1, 2);
      const float i0 = __fdividef(2.0f, l0), i1 = __fdividef(2.0f, l1);
      if (warp == 0) service(false, 4);
      if (item < 7) grp_wait(item + 1, 0, false);
      wg_wait<0>();
      fence_regs(O); fence_regs(S0); fence_regs(S1);
      char* op = (char*)g_o + (size_t)(mt * 16 + (head >> 1)) * 16384 + (8 * (item & 1) + 2 * warp) * 1024 + (4 * (head & 1) + q) * 128 + r * 16;
      st_global16(op, pack_bf16(O[0] * i0, O[1] * i0), pack_bf16(O[4] * i0, O[5] * i0), pack_bf16(O[8] * i0, O[9] * i0), pack_bf16(O[12] * i0, O[13] * i0));
      st_global16(op + 1024, pack_bf16(O[2] * i1, O[3] * i1), pack_bf16(O[6] * i1, O[7] * i1), pack_bf16(O[10] * i1, O[11] * i1), pack_bf16(O[14] * i1, O[15] * i1));
      if (lane == 0 && warp == 0) TR(24 + item);
    }
    bar_sync(2, 128);
    if (warp == 0) {
      if (elect_one()) {
        flag_signal(C_O + mt * 2 + (g >> 2));
        TR(6);
        mbar_expect_tx(bars + B_XFULL, 32768);
        tma2d(sbase + OFF_RING, &tmX, nt2 * 256 + rank * 128, mt2 * 128, bars + B_XFULL);
        tma2d(sbase + OFF_RING + 16384, &tmX, nt2 * 256 + rank * 128 + 64, mt2 * 128, bars + B_XFULL);
      }
      __syncwarp();
      service(true, 5);
      unsigned old = 0;
      if (lane == 0) asm volatile("atom.acq_rel.gpu.global.add.u32 %0, [%1], 1;" : "=r"(old) : "l"(g_cnt + C_DONE * 8) : "memory");
      if (__shfl_sync(0xffffffffu, old, 0) == gridDim.x - 1) {
        for (int i = lane; i < C_NUM; i += 32) g_cnt[i * 8] = 0;
      }
      if (lane == 0) TR(7);
    }
  } else {
    const int c = wg - 1;
    bar_sync(1, 384);
    auto first_loads = [&](int s0, int s1) {
      if (wid < 9 && elect_one()) {
#pragma unroll
        for (int s = s0; s < s1; s++) {
          if (wid == 8) tma2d(sbase + s * STAGE_BYTES, &tmX, 64 * s, mt * 128, bars + B_FULL + s * 8);
          else load_b0(s, wid - 4, sbase + s * STAGE_BYTES + 16384, bars + B_FULL + s * 8, &tmQKV, g);
        }
      }
      __syncwarp();
    };
    first_loads(0, 1);
    cluster_arrive_relaxed();
    cluster_wait();
    first_loads(1, STAGES);
    const int w = wid - 4;
    float acc[128];
    int nb = 0;
    Loader ld{nullptr, 0, 0, 3, 0, 0, false, false};
#pragma unroll 1
    for (int t = 0;; t++) {
      const int L = 16 * t + 15;
      gemm_steps(acc, ld, t < 5, nb, t < 5 ? L : 114, sbase, c, w, maps, g, rank, mt, mt2);
      if (t == 5) break;
      nb = L + 2;
      wait_full(sbase, L);
      wg_wait<0>();
      fence_regs(acc);
      wg_fence();
      half_step<0>(acc, sbase, 3, c, true, 1);
      wg_commit();
      half_step<1>(acc, sbase, 3, c, true, 1);
      wg_commit();
      release(ld, bars + B_FULL + 16);
      refill(ld, bars + B_FULL + 16, 1, 2 * (STAGE_BYTES >> 4), w);
      const int q = tid_now() & 3, r = (tid_now() & 31) >> 2;
      char* hp = (char*)g_h + (size_t)(mt * 56 + (t == 1 ? g - 1 : 16 * t - 24 + 2 * g)) * 16384 + w * 2048 + q * 128 + r * 16;
      wg_wait<1>();
      fence_half<0>(acc);
      TRT(8 + 2 * t, 256);
      if (t == 0) {
        mbar_wait(bars + B_ST, 0);
        ln_apply<0>(acc, smem_raw, w * 16 + r, q);
      }
      if (t == 0) {
        const uint32_t p = sbase + OFF_RING + w * 4096 + q * 128 + r * 16;
#pragma unroll
        for (int hh = 0; hh < 4; hh++) {
          const float* a = acc + 16 * hh;
          st_shared16(p + hh * 1024, pack_bf16(a[0], a[1]), pack_bf16(a[4], a[5]), pack_bf16(a[8], a[9]), pack_bf16(a[12], a[13]));
          st_shared16(p + hh * 1024 + 512, pack_bf16(a[2], a[3]), pack_bf16(a[6], a[7]), pack_bf16(a[10], a[11]), pack_bf16(a[14], a[15]));
        }
        asm volatile("fence.proxy.async.shared::cta;" ::: "memory");
      } else if (t == 1) {
        head_store<0>(acc, head_ptr(0, g, mt, w) + q * 128 + r * 16);
        __syncwarp();
        if (elect_one()) mbar_arrive(bars + B_EPI + 8);
      } else {
        glu_store<0>(acc, hp);
      }
      fence_half<0>(acc);
      wait_full(sbase, L + 1);
      wg_fence();
      half_step<0>(acc, sbase, 0, c, t < 4, 0);
      wg_commit();
      wg_wait<1>();
      fence_half<64>(acc);
      release(ld, bars + B_FULL + 24);
      if (t == 0) {
        ln_apply<64>(acc, smem_raw, w * 16 + r, q);
        head_store<64>(acc, head_ptr(2, g, mt, w) + q * 128 + r * 16);
      } else {
        glu_store<64>(acc, hp + 16384);
        __syncwarp();
        if (t >= 3 && elect_one()) mbar_arrive(bars + B_EPI + (t - 1) * 8);
      }
      fence_half<64>(acc);
      __syncwarp();
      TRT(9 + 2 * t, 256);
      wg_fence();
      half_step<1>(acc, sbase, 0, c, t < 4, 0);
      wg_commit();
      refill(ld, bars + B_FULL + 24, 1, 3 * (STAGE_BYTES >> 4), w);
    }
    TRT(18, 256);
    const int lane = tid_now() & 31, ct = tid_now() & 127;
    if (ct == 0) mbar_arrive_remote(mapa(bars + B_PDONE, rank ^ 1));
    wait_full(sbase, 114); wait_full(sbase, 115);
    wg_wait<0>();
    fence_regs(acc);
    wg_fence();
    half_step<1>(acc, sbase, 2, c, false, 1);
    half_step<1>(acc, sbase, 3, c, false, 1);
    wg_commit();
    half_step<0>(acc, sbase, 2, c, false, 1);
    wg_commit();
    mbar_wait_cluster(bars + B_PDONE, 0);
    {
      const uint32_t dst = mapa(sbase + c * 16384 + ct * 16, rank ^ 1), rbar = mapa(bars + B_XCH + c * 8, rank ^ 1);
      wg_wait<1>();
      fence_half<64>(acc);
#pragma unroll
      for (int i = 0; i < 8; i++) {
        if (i == 4) {
          wg_fence();
          half_step<0>(acc, sbase, 3, c, false, 1);
          wg_commit();
        }
        const float* a = acc + 64 + 8 * i;
        asm volatile("st.async.weak.shared::cluster.mbarrier::complete_tx::bytes.v4.b32 [%0], {%1, %2, %3, %4}, [%5];"
                     ::"r"(dst + i * 2048), "r"(pack_bf16(a[0], a[1])), "r"(pack_bf16(a[2], a[3])), "r"(pack_bf16(a[4], a[5])), "r"(pack_bf16(a[6], a[7])), "r"(rbar) : "memory");
      }
    }
    TRT(19, 256);
    mbar_wait(bars + B_XFULL, 0);
    mbar_wait_cluster(bars + B_XCH + c * 8, 0);
    wg_wait<0>();
    fence_half<0>(acc);
    TRT(20, 256);
    {
      const int R = c * 64 + warp * 16 + ((lane >> 3) & 1) * 8 + (lane & 7);
      const uint32_t xrow = sbase + OFF_RING + R * 128;
#pragma unroll
      for (int jj = 0; jj < 8; jj++) {
        uint32_t p0, p1, p2, p3, x0, x1, x2, x3;
        asm volatile("ld.shared.v4.b32 {%0, %1, %2, %3}, [%4];" : "=r"(p0), "=r"(p1), "=r"(p2), "=r"(p3) : "r"(sbase + c * 16384 + ct * 16 + jj * 2048));
        const uint32_t addr = xrow + (jj >> 2) * 16384 + (((((2 * jj) & 7) + (lane >> 4)) ^ (lane & 7)) << 4);
        asm volatile("ldmatrix.sync.aligned.m8n8.x4.shared.b16 {%0, %1, %2, %3}, [%4];" : "=r"(x0), "=r"(x1), "=r"(x2), "=r"(x3) : "r"(addr));
        const float* a = acc + 8 * jj;
        x0 = pack_bf16(a[0] + bf_lo(p0) + bf_lo(x0), a[1] + bf_hi(p0) + bf_hi(x0));
        x1 = pack_bf16(a[2] + bf_lo(p1) + bf_lo(x1), a[3] + bf_hi(p1) + bf_hi(x1));
        x2 = pack_bf16(a[4] + bf_lo(p2) + bf_lo(x2), a[5] + bf_hi(p2) + bf_hi(x2));
        x3 = pack_bf16(a[6] + bf_lo(p3) + bf_lo(x3), a[7] + bf_hi(p3) + bf_hi(x3));
        asm volatile("stmatrix.sync.aligned.m8n8.x4.shared.b16 [%0], {%1, %2, %3, %4};" ::"r"(addr), "r"(x0), "r"(x1), "r"(x2), "r"(x3) : "memory");
        if ((jj & 3) == 3) {
          asm volatile("fence.proxy.async.shared::cta;" ::: "memory");
          __syncwarp();
          if (lane == 0) {
            tma2d_store(&tmOut, sbase + OFF_RING + (c * 64 + warp * 16) * 128 + (jj >> 2) * 16384, nt2 * 256 + rank * 128 + (jj >> 2) * 64, mt2 * 128 + c * 64 + warp * 16);
            asm volatile("cp.async.bulk.commit_group;" ::: "memory");
          }
        }
      }
      if (lane == 0) asm volatile("cp.async.bulk.wait_group.read 0;" ::: "memory");
    }
    TRT(21, 256);
    TRG(62, 256);
  }
}

typedef CUresult (*EncodeFn)(CUtensorMap*, CUtensorMapDataType, cuuint32_t, void*, const cuuint64_t*, const cuuint64_t*, const cuuint32_t*,
                             const cuuint32_t*, CUtensorMapInterleave, CUtensorMapSwizzle, CUtensorMapL2promotion, CUtensorMapFloatOOBfill);

void make_map2d(EncodeFn enc, CUtensorMap* m, const void* ptr, uint64_t cols, uint64_t rows, uint32_t boxc, uint32_t boxr) {
  cuuint64_t gd[2] = {cols, rows}, gs[1] = {cols * 2};
  cuuint32_t box[2] = {boxc, boxr}, es[2] = {1, 1};
  enc(m, CU_TENSOR_MAP_DATA_TYPE_BFLOAT16, 2, const_cast<void*>(ptr), gd, gs, box, es, CU_TENSOR_MAP_INTERLEAVE_NONE, CU_TENSOR_MAP_SWIZZLE_128B,
      CU_TENSOR_MAP_L2_PROMOTION_L2_256B, CU_TENSOR_MAP_FLOAT_OOB_FILL_NONE);
}

void make_map_w(EncodeFn enc, CUtensorMap* m, const void* ptr, uint64_t cols, uint64_t rows, bool permute) {
  const cuuint64_t p = cols * 2;
  cuuint64_t gd[5] = {cols, 2, 4, 4, rows / 32}, gs[4] = {p, (permute ? 8 : 2) * p, (permute ? 2 : 8) * p, 32 * p};
  cuuint32_t box[5] = {64, 2, 4, 4, 2}, es[5] = {1, 1, 1, 1, 1};
  enc(m, CU_TENSOR_MAP_DATA_TYPE_BFLOAT16, 5, const_cast<void*>(ptr), gd, gs, box, es, CU_TENSOR_MAP_INTERLEAVE_NONE, CU_TENSOR_MAP_SWIZZLE_128B,
      CU_TENSOR_MAP_L2_PROMOTION_L2_256B, CU_TENSOR_MAP_FLOAT_OOB_FILL_NONE);
}

}

extern "C" void kernel_launch(void* const* d_in, const int* in_sizes, int n_in, void* d_out, int out_size) {
  (void)in_sizes; (void)n_in; (void)out_size;
  static EncodeFn enc = nullptr;
  if (!enc) {
    void* fn = nullptr;
    cudaDriverEntryPointQueryResult qr;
    cudaGetDriverEntryPoint("cuTensorMapEncodeTiled", &fn, cudaEnableDefault, &qr);
    enc = (EncodeFn)fn;
    cudaFuncSetAttribute(fused_kernel, cudaFuncAttributeMaxDynamicSharedMemorySize, SMEM_BYTES);
  }
  CUtensorMap tmQKV, tmG, tmU, tmD, tmO, tmX, tmOut;
  make_map_w(enc, &tmQKV, d_in[1], 3072, 1024, false);
  make_map_w(enc, &tmG, d_in[4], 3584, 1024, false);
  make_map_w(enc, &tmU, d_in[5], 3584, 1024, false);
  make_map_w(enc, &tmO, d_in[2], 1024, 1024, false);
  make_map_w(enc, &tmD, d_in[6], 1024, 3584, true);
  make_map2d(enc, &tmX, d_in[0], 1024, 2048, 64, 128);
  make_map2d(enc, &tmOut, d_out, 1024, 2048, 64, 16);
  fused_kernel<<<128, 384, SMEM_BYTES>>>(tmQKV, tmG, tmU, tmD, tmO, tmX, tmOut, (const uint4*)d_in[0], (const uint4*)d_in[1]);
}
```
